```python
import torch

def _softmax(x, axis=-1):
    return torch.softmax(x, dim=axis)
def _gelu(x):
    return torch.nn.functional.gelu(x, approximate="tanh")
def _silu(x):
    return torch.nn.functional.silu(x)
def _sigmoid(x):
    return torch.sigmoid(x)
def _layernorm(x, axis=-1, eps=1e-5):
    m = x.mean(dim=axis, keepdim=True)
    v = x.var(dim=axis, keepdim=True, unbiased=False)
    return (x - m) / torch.sqrt(v + eps)
def _scatter_add(tgt, idx, src, axis=0):
    return tgt.clone().index_add_(axis, idx, src)
def _segment_sum(src, seg, n):
    out = torch.zeros((n,) + src.shape[1:], dtype=src.dtype)
    return out.index_add_(0, seg, src)
def _pad(x, pw):
    flat = tuple(v for pair in reversed(pw) for v in pair)
    return torch.nn.functional.pad(x, flat)

kernel_name = 'gated_mix__sliding_local_dilated__dense_activation_mish__prompt'

def setup_inputs():

    _w = (lambda a: (lambda t: t.to(torch.bfloat16) if t.is_floating_point() else t)(torch.as_tensor(a)))
    def _A_setup():
        B, S, D = 1, 2048, 640
        return {
            "x": _w((lambda *s: torch.randn(*s, dtype=torch.bfloat16) * 0.05)(B, S, D)),
            "wqkv": _w((lambda *s: torch.randn(*s, dtype=torch.bfloat16) * 0.8)(D, 3 * D)),
            "wo": _w((lambda *s: torch.randn(*s, dtype=torch.bfloat16) * 0.05)(D, D)),
        }
    _A_in = _A_setup()

    def _B_setup():
        B, S, D, F = 1, 2048, 640, 1728
        return {
            "x": _w((lambda *s: torch.randn(*s, dtype=torch.bfloat16) * 0.05)(B, S, D)),
            "w1": _w((lambda *s: torch.randn(*s, dtype=torch.bfloat16) * 12.8)(D, F) * (D ** -0.5)),
            "b1": _w((lambda *s: torch.randn(*s, dtype=torch.bfloat16) * 0.8)(F)),
            "w2": _w((lambda *s: torch.randn(*s, dtype=torch.bfloat16) * 0.8)(F, D) * (F ** -0.5)),
        }
    _B_in = _B_setup()

    return {
        "A_x": _A_in["x"],
        "A_wqkv": _A_in["wqkv"],
        "A_wo": _A_in["wo"],
        "B_x": _B_in["x"],
        "B_w1": _B_in["w1"],
        "B_b1": _B_in["b1"],
        "B_w2": _B_in["w2"],
        "gate_w": _w((lambda *s: torch.randn(*s, dtype=torch.bfloat16) * 0.05)(640) * 16.0),
    }

def reference(A_x, A_wqkv, A_wo, B_x, B_w1, B_b1, B_w2, gate_w):
    def _A_ref(x, wqkv, wo):
        B, S, D = x.shape
        H = 32; Dh = D // H
        W, dil = 8, 2
        qkv = (lambda x, *d: x.permute(*d))((x @ wqkv).reshape(B, S, 3, H, Dh), 2, 0, 3, 1, 4)
        q, k, v = qkv[0], qkv[1], qkv[2]
        scale = Dh ** -0.5
        pos = torch.arange(S)
        off = torch.arange(W) * dil
        idx = pos[:, None] - off[None, :]
        mask = idx >= 0
        idx_c = torch.where(mask, idx, 0).reshape(-1)
        kg = k[:, :, idx_c, :].reshape(B, H, S, W, Dh)
        vg = v[:, :, idx_c, :].reshape(B, H, S, W, Dh)
        logits = torch.einsum("bhsd,bhswd->bhsw", q, kg) * scale
        logits = torch.where(mask[None, None, :, :], logits, -1e9)
        attn = _softmax(logits, axis=-1)
        o = torch.einsum("bhsw,bhswd->bhsd", attn, vg)
        return (lambda x, *d: x.permute(*d))(o, 0, 2, 1, 3).reshape(B, S, D) @ wo

    def _B_ref(x, w1, b1, w2):
        h = torch.einsum("bsd,df->bsf", x, w1) + b1
        sp = torch.log1p(torch.exp(-torch.abs(h))) + torch.where(h > 0, h, torch.zeros_like(h))
        act = h * torch.tanh(sp)
        return torch.einsum("bsf,fd->bsd", act, w2)

    x = A_x
    g = _sigmoid((x * gate_w).sum(-1, keepdims=True))
    a = _A_ref(x, A_wqkv, A_wo)
    b = _B_ref(x, B_w1, B_b1, B_w2)
    return g * a + (1 - g) * b
```

```cpp
#include <cuda_runtime.h>
#include <cuda_bf16.h>
#include <cuda.h>
#include <stdint.h>

namespace {

constexpr int SEQ = 2048, DM = 640, FF = 1728, NQKV = 1920, KA2 = 2368;
constexpr int N1A = 240, N1B = 216, N2 = 160;
constexpr int P1_SLOT = 49152;
constexpr int P2_SLOT = 40960;
constexpr int RED_OFF = 163840;
constexpr int CTRL_OFF = 204800;
constexpr int SMEM_BYTES = CTRL_OFF + 1024 + 1024;
constexpr unsigned SPIN_LIMIT = 1u << 24;

__device__ __align__(1024) __nv_bfloat16 g_qkv[SEQ * NQKV];
__device__ __align__(1024) __nv_bfloat16 g_a2[SEQ * KA2];
__device__ unsigned int g_flags[64];

__device__ __forceinline__ uint32_t s32(const void* p) { return (uint32_t)__cvta_generic_to_shared(p); }
__device__ __forceinline__ void mbar_init(uint32_t b, uint32_t c) {
  asm volatile("mbarrier.init.shared::cta.b64 [%0], %1;" ::"r"(b), "r"(c) : "memory");
}
__device__ __forceinline__ void mbar_expect_tx(uint32_t b, uint32_t bytes) {
  asm volatile("mbarrier.arrive.expect_tx.shared::cta.b64 _, [%0], %1;" ::"r"(b), "r"(bytes) : "memory");
}
__device__ __forceinline__ void mbar_arrive(uint32_t b) {
  asm volatile("mbarrier.arrive.shared::cta.b64 _, [%0];" ::"r"(b) : "memory");
}
__device__ __forceinline__ void mbar_arrive_cnt(uint32_t b, uint32_t c) {
  asm volatile("mbarrier.arrive.shared::cta.b64 _, [%0], %1;" ::"r"(b), "r"(c) : "memory");
}
__device__ __forceinline__ void mbar_wait(uint32_t b, uint32_t parity) {
  uint32_t ok = 0;
  for (unsigned it = 0; it < SPIN_LIMIT && !ok; ++it) {
    asm volatile("{\n.reg .pred p;\nmbarrier.try_wait.parity.shared::cta.b64 p, [%1], %2;\nselp.u32 %0, 1, 0, p;\n}"
                 : "=r"(ok) : "r"(b), "r"(parity) : "memory");
  }
}
__device__ __forceinline__ void mbar_wait_cluster(uint32_t b, uint32_t parity) {
  uint32_t ok = 0;
  for (unsigned it = 0; it < SPIN_LIMIT && !ok; ++it) {
    asm volatile("{\n.reg .pred p;\nmbarrier.try_wait.parity.acquire.cluster.shared::cta.b64 p, [%1], %2;\nselp.u32 %0, 1, 0, p;\n}"
                 : "=r"(ok) : "r"(b), "r"(parity) : "memory");
  }
}
__device__ __forceinline__ void tma_load(uint32_t dst, const CUtensorMap* tm, uint32_t bar, int c0, int c1) {
  asm volatile("cp.async.bulk.tensor.2d.shared::cluster.global.mbarrier::complete_tx::bytes [%0], [%1, {%3, %4}], [%2];"
               ::"r"(dst), "l"(tm), "r"(bar), "r"(c0), "r"(c1) : "memory");
}
__device__ __forceinline__ void tma_store(const CUtensorMap* tm, uint32_t src, int c0, int c1) {
  asm volatile("cp.async.bulk.tensor.2d.global.shared::cta.bulk_group [%0, {%2, %3}], [%1];"
               ::"l"(tm), "r"(src), "r"(c0), "r"(c1) : "memory");
}
__device__ __forceinline__ void prefetch_tmap(const CUtensorMap* tm) {
  asm volatile("prefetch.tensormap [%0];" ::"l"(tm) : "memory");
}
__device__ __forceinline__ void wgmma_fence() { asm volatile("wgmma.fence.sync.aligned;" ::: "memory"); }
__device__ __forceinline__ void wgmma_commit() { asm volatile("wgmma.commit_group.sync.aligned;" ::: "memory"); }
template <int N> __device__ __forceinline__ void wgmma_wait() { asm volatile("wgmma.wait_group.sync.aligned %0;" ::"n"(N) : "memory"); }
__device__ __forceinline__ void bar_sync(int id, int n) { asm volatile("bar.sync %0, %1;" ::"r"(id), "r"(n) : "memory"); }
__device__ __forceinline__ void fence_async_smem() { asm volatile("fence.proxy.async.shared::cta;" ::: "memory"); }
__device__ __forceinline__ void fence_async_all() { asm volatile("fence.proxy.async;" ::: "memory"); }
__device__ __forceinline__ void flag_signal(unsigned int* f) {
  asm volatile("fence.acq_rel.gpu;\nred.release.gpu.global.add.u32 [%0], 1;" ::"l"(f) : "memory");
}
__device__ __forceinline__ void flag_wait(const unsigned int* f, unsigned int target) {
  unsigned int v = 0;
  for (unsigned it = 0; it < SPIN_LIMIT; ++it) {
    asm volatile("ld.acquire.gpu.global.u32 %0, [%1];" : "=r"(v) : "l"(f) : "memory");
    if (v >= target) break;
  }
}
__device__ __forceinline__ uint64_t desc_a(uint32_t addr) {
  return (uint64_t)((addr & 0x3FFFF) >> 4) | ((uint64_t)1 << 16) | ((uint64_t)64 << 32) | ((uint64_t)1 << 62);
}
__device__ __forceinline__ uint64_t desc_b(uint32_t addr) {
  return (uint64_t)((addr & 0x3FFFF) >> 4) | ((uint64_t)512 << 16) | ((uint64_t)64 << 32) | ((uint64_t)1 << 62);
}
__device__ __forceinline__ uint32_t pack_bf16(float lo, float hi) {
  __nv_bfloat162 v = __floats2bfloat162_rn(lo, hi);
  return *reinterpret_cast<uint32_t*>(&v);
}
__device__ __forceinline__ void stsm_x4(uint32_t addr, uint32_t r0, uint32_t r1, uint32_t r2, uint32_t r3) {
  asm volatile("stmatrix.sync.aligned.m8n8.x4.shared.b16 [%0], {%1, %2, %3, %4};" ::"r"(addr), "r"(r0), "r"(r1), "r"(r2), "r"(r3) : "memory");
}
__device__ __forceinline__ void stsm_x2(uint32_t addr, uint32_t r0, uint32_t r1) {
  asm volatile("stmatrix.sync.aligned.m8n8.x2.shared.b16 [%0], {%1, %2};" ::"r"(addr), "r"(r0), "r"(r1) : "memory");
}
__device__ __forceinline__ float bf_lo(uint32_t v) { return __uint_as_float(v << 16); }
__device__ __forceinline__ float bf_hi(uint32_t v) { return __uint_as_float(v & 0xFFFF0000u); }

__device__ __forceinline__ float mish(float h) {
  float n = __expf(-fabsf(h));
  float n2 = n * n;
  float t = 2.f * n;
  float num = (h > 0.f) ? (1.f + t) : (n2 + t);
  float den = (h > 0.f) ? (num + 2.f * n2) : (num + 2.f);
  return h * __fdividef(num, den);
}

__device__ __forceinline__ void wgmma_n240(float (&d)[120], uint64_t da, uint64_t db, int scale_d) {
  asm volatile("{\n.reg .pred p;\nsetp.ne.b32 p, %122, 0;\n"
    "wgmma.mma_async.sync.aligned.m64n240k16.f32.bf16.bf16 {%0, %1, %2, %3, %4, %5, %6, %7, %8, %9, %10, %11, %12, %13, %14, %15, %16, %17, %18, %19, %20, %21, %22, %23, %24, %25, %26, %27, %28, %29, %30, %31, %32, %33, %34, %35, %36, %37, %38, %39, %40, %41, %42, %43, %44, %45, %46, %47, %48, %49, %50, %51, %52, %53, %54, %55, %56, %57, %58, %59, %60, %61, %62, %63, %64, %65, %66, %67, %68, %69, %70, %71, %72, %73, %74, %75, %76, %77, %78, %79, %80, %81, %82, %83, %84, %85, %86, %87, %88, %89, %90, %91, %92, %93, %94, %95, %96, %97, %98, %99, %100, %101, %102, %103, %104, %105, %106, %107, %108, %109, %110, %111, %112, %113, %114, %115, %116, %117, %118, %119}, %120, %121, p, 1, 1, 0, 1;\n}\n"
    : "+f"(d[0]), "+f"(d[1]), "+f"(d[2]), "+f"(d[3]), "+f"(d[4]), "+f"(d[5]), "+f"(d[6]), "+f"(d[7]), "+f"(d[8]), "+f"(d[9]), "+f"(d[10]), "+f"(d[11]), "+f"(d[12]), "+f"(d[13]), "+f"(d[14]), "+f"(d[15]), "+f"(d[16]), "+f"(d[17]), "+f"(d[18]), "+f"(d[19]), "+f"(d[20]), "+f"(d[21]), "+f"(d[22]), "+f"(d[23]), "+f"(d[24]), "+f"(d[25]), "+f"(d[26]), "+f"(d[27]), "+f"(d[28]), "+f"(d[29]), "+f"(d[30]), "+f"(d[31]), "+f"(d[32]), "+f"(d[33]), "+f"(d[34]), "+f"(d[35]), "+f"(d[36]), "+f"(d[37]), "+f"(d[38]), "+f"(d[39]), "+f"(d[40]), "+f"(d[41]), "+f"(d[42]), "+f"(d[43]), "+f"(d[44]), "+f"(d[45]), "+f"(d[46]), "+f"(d[47]), "+f"(d[48]), "+f"(d[49]), "+f"(d[50]), "+f"(d[51]), "+f"(d[52]), "+f"(d[53]), "+f"(d[54]), "+f"(d[55]), "+f"(d[56]), "+f"(d[57]), "+f"(d[58]), "+f"(d[59]), "+f"(d[60]), "+f"(d[61]), "+f"(d[62]), "+f"(d[63]), "+f"(d[64]), "+f"(d[65]), "+f"(d[66]), "+f"(d[67]), "+f"(d[68]), "+f"(d[69]), "+f"(d[70]), "+f"(d[71]), "+f"(d[72]), "+f"(d[73]), "+f"(d[74]), "+f"(d[75]), "+f"(d[76]), "+f"(d[77]), "+f"(d[78]), "+f"(d[79]), "+f"(d[80]), "+f"(d[81]), "+f"(d[82]), "+f"(d[83]), "+f"(d[84]), "+f"(d[85]), "+f"(d[86]), "+f"(d[87]), "+f"(d[88]), "+f"(d[89]), "+f"(d[90]), "+f"(d[91]), "+f"(d[92]), "+f"(d[93]), "+f"(d[94]), "+f"(d[95]), "+f"(d[96]), "+f"(d[97]), "+f"(d[98]), "+f"(d[99]), "+f"(d[100]), "+f"(d[101]), "+f"(d[102]), "+f"(d[103]), "+f"(d[104]), "+f"(d[105]), "+f"(d[106]), "+f"(d[107]), "+f"(d[108]), "+f"(d[109]), "+f"(d[110]), "+f"(d[111]), "+f"(d[112]), "+f"(d[113]), "+f"(d[114]), "+f"(d[115]), "+f"(d[116]), "+f"(d[117]), "+f"(d[118]), "+f"(d[119])
    : "l"(da), "l"(db), "r"(scale_d));
}

__device__ __forceinline__ void wgmma_n216(float (&d)[108], uint64_t da, uint64_t db, int scale_d) {
  asm volatile("{\n.reg .pred p;\nsetp.ne.b32 p, %110, 0;\n"
    "wgmma.mma_async.sync.aligned.m64n216k16.f32.bf16.bf16 {%0, %1, %2, %3, %4, %5, %6, %7, %8, %9, %10, %11, %12, %13, %14, %15, %16, %17, %18, %19, %20, %21, %22, %23, %24, %25, %26, %27, %28, %29, %30, %31, %32, %33, %34, %35, %36, %37, %38, %39, %40, %41, %42, %43, %44, %45, %46, %47, %48, %49, %50, %51, %52, %53, %54, %55, %56, %57, %58, %59, %60, %61, %62, %63, %64, %65, %66, %67, %68, %69, %70, %71, %72, %73, %74, %75, %76, %77, %78, %79, %80, %81, %82, %83, %84, %85, %86, %87, %88, %89, %90, %91, %92, %93, %94, %95, %96, %97, %98, %99, %100, %101, %102, %103, %104, %105, %106, %107}, %108, %109, p, 1, 1, 0, 1;\n}\n"
    : "+f"(d[0]), "+f"(d[1]), "+f"(d[2]), "+f"(d[3]), "+f"(d[4]), "+f"(d[5]), "+f"(d[6]), "+f"(d[7]), "+f"(d[8]), "+f"(d[9]), "+f"(d[10]), "+f"(d[11]), "+f"(d[12]), "+f"(d[13]), "+f"(d[14]), "+f"(d[15]), "+f"(d[16]), "+f"(d[17]), "+f"(d[18]), "+f"(d[19]), "+f"(d[20]), "+f"(d[21]), "+f"(d[22]), "+f"(d[23]), "+f"(d[24]), "+f"(d[25]), "+f"(d[26]), "+f"(d[27]), "+f"(d[28]), "+f"(d[29]), "+f"(d[30]), "+f"(d[31]), "+f"(d[32]), "+f"(d[33]), "+f"(d[34]), "+f"(d[35]), "+f"(d[36]), "+f"(d[37]), "+f"(d[38]), "+f"(d[39]), "+f"(d[40]), "+f"(d[41]), "+f"(d[42]), "+f"(d[43]), "+f"(d[44]), "+f"(d[45]), "+f"(d[46]), "+f"(d[47]), "+f"(d[48]), "+f"(d[49]), "+f"(d[50]), "+f"(d[51]), "+f"(d[52]), "+f"(d[53]), "+f"(d[54]), "+f"(d[55]), "+f"(d[56]), "+f"(d[57]), "+f"(d[58]), "+f"(d[59]), "+f"(d[60]), "+f"(d[61]), "+f"(d[62]), "+f"(d[63]), "+f"(d[64]), "+f"(d[65]), "+f"(d[66]), "+f"(d[67]), "+f"(d[68]), "+f"(d[69]), "+f"(d[70]), "+f"(d[71]), "+f"(d[72]), "+f"(d[73]), "+f"(d[74]), "+f"(d[75]), "+f"(d[76]), "+f"(d[77]), "+f"(d[78]), "+f"(d[79]), "+f"(d[80]), "+f"(d[81]), "+f"(d[82]), "+f"(d[83]), "+f"(d[84]), "+f"(d[85]), "+f"(d[86]), "+f"(d[87]), "+f"(d[88]), "+f"(d[89]), "+f"(d[90]), "+f"(d[91]), "+f"(d[92]), "+f"(d[93]), "+f"(d[94]), "+f"(d[95]), "+f"(d[96]), "+f"(d[97]), "+f"(d[98]), "+f"(d[99]), "+f"(d[100]), "+f"(d[101]), "+f"(d[102]), "+f"(d[103]), "+f"(d[104]), "+f"(d[105]), "+f"(d[106]), "+f"(d[107])
    : "l"(da), "l"(db), "r"(scale_d));
}

__device__ __forceinline__ void wgmma_n160(float (&d)[80], uint64_t da, uint64_t db, int scale_d) {
  asm volatile("{\n.reg .pred p;\nsetp.ne.b32 p, %82, 0;\n"
    "wgmma.mma_async.sync.aligned.m64n160k16.f32.bf16.bf16 {%0, %1, %2, %3, %4, %5, %6, %7, %8, %9, %10, %11, %12, %13, %14, %15, %16, %17, %18, %19, %20, %21, %22, %23, %24, %25, %26, %27, %28, %29, %30, %31, %32, %33, %34, %35, %36, %37, %38, %39, %40, %41, %42, %43, %44, %45, %46, %47, %48, %49, %50, %51, %52, %53, %54, %55, %56, %57, %58, %59, %60, %61, %62, %63, %64, %65, %66, %67, %68, %69, %70, %71, %72, %73, %74, %75, %76, %77, %78, %79}, %80, %81, p, 1, 1, 0, 1;\n}\n"
    : "+f"(d[0]), "+f"(d[1]), "+f"(d[2]), "+f"(d[3]), "+f"(d[4]), "+f"(d[5]), "+f"(d[6]), "+f"(d[7]), "+f"(d[8]), "+f"(d[9]), "+f"(d[10]), "+f"(d[11]), "+f"(d[12]), "+f"(d[13]), "+f"(d[14]), "+f"(d[15]), "+f"(d[16]), "+f"(d[17]), "+f"(d[18]), "+f"(d[19]), "+f"(d[20]), "+f"(d[21]), "+f"(d[22]), "+f"(d[23]), "+f"(d[24]), "+f"(d[25]), "+f"(d[26]), "+f"(d[27]), "+f"(d[28]), "+f"(d[29]), "+f"(d[30]), "+f"(d[31]), "+f"(d[32]), "+f"(d[33]), "+f"(d[34]), "+f"(d[35]), "+f"(d[36]), "+f"(d[37]), "+f"(d[38]), "+f"(d[39]), "+f"(d[40]), "+f"(d[41]), "+f"(d[42]), "+f"(d[43]), "+f"(d[44]), "+f"(d[45]), "+f"(d[46]), "+f"(d[47]), "+f"(d[48]), "+f"(d[49]), "+f"(d[50]), "+f"(d[51]), "+f"(d[52]), "+f"(d[53]), "+f"(d[54]), "+f"(d[55]), "+f"(d[56]), "+f"(d[57]), "+f"(d[58]), "+f"(d[59]), "+f"(d[60]), "+f"(d[61]), "+f"(d[62]), "+f"(d[63]), "+f"(d[64]), "+f"(d[65]), "+f"(d[66]), "+f"(d[67]), "+f"(d[68]), "+f"(d[69]), "+f"(d[70]), "+f"(d[71]), "+f"(d[72]), "+f"(d[73]), "+f"(d[74]), "+f"(d[75]), "+f"(d[76]), "+f"(d[77]), "+f"(d[78]), "+f"(d[79])
    : "l"(da), "l"(db), "r"(scale_d));
}


__global__ void __cluster_dims__(2, 1, 1) __launch_bounds__(384, 1)
fused_kernel(const __grid_constant__ CUtensorMap tm_x, const __grid_constant__ CUtensorMap tm_wqkv,
             const __grid_constant__ CUtensorMap tm_w1, const __grid_constant__ CUtensorMap tm_a2,
             const __grid_constant__ CUtensorMap tm_wo, const __grid_constant__ CUtensorMap tm_w2,
             const __grid_constant__ CUtensorMap tm_qkv_st, const __grid_constant__ CUtensorMap tm_act_st,
             const __nv_bfloat16* __restrict__ x, const __nv_bfloat16* __restrict__ b1,
             const __nv_bfloat16* __restrict__ gate_w, __nv_bfloat16* __restrict__ out) {
  extern __shared__ uint8_t smem_raw[];
  const uint32_t sbase = (s32(smem_raw) + 1023u) & ~1023u;
  uint8_t* sgen = smem_raw + (sbase - s32(smem_raw));
  const uint32_t bar_full = sbase + CTRL_OFF;
  const uint32_t bar_empty = bar_full + 32;
  const uint32_t bar_stg = bar_full + 64;
  const uint32_t bar_g = bar_full + 72;
  const uint32_t bar_red = bar_full + 80;
  float* g_s = reinterpret_cast<float*>(sgen + CTRL_OFF + 128);

  const int tid = threadIdx.x;
  const int rb = blockIdx.x >> 3;
  const int j = blockIdx.x & 7;
  const int ns = j >> 1, kh = j & 1;
  const int row0 = rb * 128;

  if (tid == 0) {
    for (int s = 0; s < 4; ++s) { mbar_init(bar_full + 8 * s, 1); mbar_init(bar_empty + 8 * s, 2); }
    mbar_init(bar_stg, 256);
    mbar_init(bar_g, 96);
    mbar_init(bar_red, 256);
    asm volatile("fence.mbarrier_init.release.cluster;" ::: "memory");
  }
  __syncthreads();
  asm volatile("barrier.cluster.arrive.release.aligned;\nbarrier.cluster.wait.acquire.aligned;" ::: "memory");

  const int wg = tid >> 7;
  if (wg < 2) {
    const int warp = (tid >> 5) & 3, lane = tid & 31;
    const bool elected = (tid & 127) == 0;
    const int st_row = wg * 64 + warp * 16 + (lane & 7) + ((lane >> 3) & 1) * 8;
    const int st_col = (lane >> 4) * 8;
    {
      float acc[N1A / 2];
#pragma unroll 1
      for (int kb = 0; kb < 10; ++kb) {
        const int slot = kb & 3;
        mbar_wait(bar_full + 8 * slot, (kb >> 2) & 1);
        const uint32_t a0 = sbase + slot * P1_SLOT + wg * 8192;
        const uint32_t b0 = sbase + slot * P1_SLOT + 16384;
        wgmma_fence();
#pragma unroll
        for (int k = 0; k < 4; ++k) wgmma_n240(acc, desc_a(a0 + k * 32), desc_b(b0 + k * 2048), (kb | k) != 0);
        wgmma_commit();
        if (kb > 0) {
          wgmma_wait<1>();
          if (elected && kb - 1 < 8) mbar_arrive(bar_empty + 8 * ((kb - 1) & 3));
        }
      }
      wgmma_wait<0>();
      bar_sync(1, 256);
      const uint32_t stg = sbase + st_row * (N1A * 2) + st_col * 2;
#pragma unroll
      for (int q = 0; q < 15; ++q) {
        stsm_x4(stg + q * 32, pack_bf16(acc[8 * q + 0], acc[8 * q + 1]), pack_bf16(acc[8 * q + 2], acc[8 * q + 3]),
                pack_bf16(acc[8 * q + 4], acc[8 * q + 5]), pack_bf16(acc[8 * q + 6], acc[8 * q + 7]));
      }
      fence_async_smem();
      mbar_arrive(bar_stg);
    }
    {
      float acc[N1B / 2];
      uint32_t bias[27];
      {
        const uint32_t* bp = reinterpret_cast<const uint32_t*>(b1 + j * N1B) + (lane & 3);
#pragma unroll
        for (int q = 0; q < 27; ++q) bias[q] = __ldg(bp + 4 * q);
      }
#pragma unroll 1
      for (int kb = 10; kb < 20; ++kb) {
        const int slot = kb & 3;
        mbar_wait(bar_full + 8 * slot, (kb >> 2) & 1);
        const uint32_t a0 = sbase + slot * P1_SLOT + wg * 8192;
        const uint32_t b0 = sbase + slot * P1_SLOT + 16384;
        wgmma_fence();
#pragma unroll
        for (int k = 0; k < 4; ++k) wgmma_n216(acc, desc_a(a0 + k * 32), desc_b(b0 + k * 2048), (kb != 10) || (k != 0));
        wgmma_commit();
        if (kb > 10) {
          wgmma_wait<1>();
          if (elected && kb - 1 < 18) mbar_arrive(bar_empty + 8 * ((kb - 1) & 3));
        }
      }
      wgmma_wait<0>();
      mbar_wait(bar_g, 0);
      const float om0 = 1.f - g_s[wg * 64 + warp * 16 + (lane >> 2)];
      const float om1 = 1.f - g_s[wg * 64 + warp * 16 + (lane >> 2) + 8];
      bar_sync(1, 256);
      const uint32_t stg = sbase + 2 * P1_SLOT + st_row * (N1B * 2) + st_col * 2;
      uint32_t pk[54];
#pragma unroll
      for (int q = 0; q < 27; ++q) {
        const float bl = bf_lo(bias[q]), bh = bf_hi(bias[q]);
        pk[2 * q + 0] = pack_bf16(mish(acc[4 * q + 0] + bl) * om0, mish(acc[4 * q + 1] + bh) * om0);
        pk[2 * q + 1] = pack_bf16(mish(acc[4 * q + 2] + bl) * om1, mish(acc[4 * q + 3] + bh) * om1);
        if (q & 1) stsm_x4(stg + (q >> 1) * 32, pk[2 * q - 2], pk[2 * q - 1], pk[2 * q], pk[2 * q + 1]);
      }
      stsm_x2(sbase + 2 * P1_SLOT + st_row * (N1B * 2) + 26 * 16, pk[52], pk[53]);
      fence_async_smem();
      mbar_arrive(bar_stg);
    }
    {
      float acc[N2 / 2];
      const int nkb = kh ? 18 : 19;
#pragma unroll 1
      for (int t = 0; t < nkb; ++t) {
        const int kb = 20 + t;
        const int slot = kb & 3;
        mbar_wait(bar_full + 8 * slot, (kb >> 2) & 1);
        const uint32_t a0 = sbase + slot * P2_SLOT + wg * 8192;
        const uint32_t b0 = sbase + slot * P2_SLOT + 16384;
        wgmma_fence();
#pragma unroll
        for (int k = 0; k < 4; ++k) wgmma_n160(acc, desc_a(a0 + k * 32), desc_b(b0 + k * 2048), (t | k) != 0);
        wgmma_commit();
        if (t > 0) {
          wgmma_wait<1>();
          if (elected) mbar_arrive(bar_empty + 8 * ((kb - 1) & 3));
        }
      }
      wgmma_wait<0>();
      uint32_t peer_red, peer_bar;
      asm volatile("mapa.shared::cluster.u32 %0, %1, %2;" : "=r"(peer_red) : "r"(sbase + RED_OFF + tid * 16), "r"(kh ^ 1));
      asm volatile("mapa.shared::cluster.u32 %0, %1, %2;" : "=r"(peer_bar) : "r"(bar_red), "r"(kh ^ 1));
#pragma unroll
      for (int q = 0; q < 10; ++q) {
        const float v0 = kh ? acc[4 * q + 0] : acc[40 + 4 * q + 0];
        const float v1 = kh ? acc[4 * q + 1] : acc[40 + 4 * q + 1];
        const float v2 = kh ? acc[4 * q + 2] : acc[40 + 4 * q + 2];
        const float v3 = kh ? acc[4 * q + 3] : acc[40 + 4 * q + 3];
        asm volatile("st.shared::cluster.v4.f32 [%0], {%1, %2, %3, %4};" ::"r"(peer_red + q * 4096), "f"(v0), "f"(v1), "f"(v2), "f"(v3) : "memory");
      }
      asm volatile("mbarrier.arrive.release.cluster.shared::cluster.b64 _, [%0];" ::"r"(peer_bar) : "memory");
      mbar_wait_cluster(bar_red, 0);
      const int r_lo = row0 + wg * 64 + warp * 16 + (lane >> 2);
      __nv_bfloat16* o0 = out + (size_t)r_lo * DM + ns * N2 + kh * 80 + (lane & 3) * 2;
      __nv_bfloat16* o1 = o0 + 8 * DM;
#pragma unroll
      for (int q = 0; q < 10; ++q) {
        const float4 p = *reinterpret_cast<const float4*>(sgen + RED_OFF + q * 4096 + tid * 16);
        const float v0 = (kh ? acc[40 + 4 * q + 0] : acc[4 * q + 0]) + p.x;
        const float v1 = (kh ? acc[40 + 4 * q + 1] : acc[4 * q + 1]) + p.y;
        const float v2 = (kh ? acc[40 + 4 * q + 2] : acc[4 * q + 2]) + p.z;
        const float v3 = (kh ? acc[40 + 4 * q + 3] : acc[4 * q + 3]) + p.w;
        *reinterpret_cast<uint32_t*>(o0 + q * 8) = pack_bf16(v0, v1);
        *reinterpret_cast<uint32_t*>(o1 + q * 8) = pack_bf16(v2, v3);
      }
      if (tid == 0) {
        const unsigned int prev = atomicInc(&g_flags[48], gridDim.x - 1);
        if (prev == gridDim.x - 1) {
          for (int f = 0; f < 48; ++f) g_flags[f] = 0;
        }
      }
    }
  } else if (tid < 288) {
    if (tid == 256) {
      prefetch_tmap(&tm_x); prefetch_tmap(&tm_wqkv); prefetch_tmap(&tm_w1);
      prefetch_tmap(&tm_a2); prefetch_tmap(&tm_wo); prefetch_tmap(&tm_w2); prefetch_tmap(&tm_act_st);
#pragma unroll 1
      for (int kb = 0; kb < 20; ++kb) {
        const int slot = kb & 3;
        mbar_wait(bar_empty + 8 * slot, ((kb >> 2) & 1) ^ 1);
        const uint32_t fb = bar_full + 8 * slot;
        const uint32_t dst = sbase + slot * P1_SLOT;
        const int kk = (kb < 10 ? kb : kb - 10) * 64;
        mbar_expect_tx(fb, 49152);
        tma_load(dst, &tm_x, fb, kk, row0);
        const CUtensorMap* tw = kb < 10 ? &tm_wqkv : &tm_w1;
        const int c0 = kb < 10 ? j * N1A : j * N1B;
#pragma unroll
        for (int c = 0; c < 4; ++c) tma_load(dst + 16384 + c * 8192, tw, fb, c0 + c * 64, kk);
      }
      const int nkb = kh ? 18 : 19;
      const int kact = kh ? 896 : 0;
#pragma unroll 1
      for (int t = 0; t < nkb; ++t) {
        const int kb = 20 + t;
        const int slot = kb & 3;
        if (t == 2) {
          mbar_wait(bar_stg, 1);
          tma_store(&tm_act_st, sbase + 2 * P1_SLOT, DM + j * N1B, row0);
          asm volatile("cp.async.bulk.commit_group;" ::: "memory");
          asm volatile("cp.async.bulk.wait_group.read 0;" ::: "memory");
          mbar_arrive_cnt(bar_empty + 16, 2);
          mbar_arrive_cnt(bar_empty + 24, 2);
        }
        if (t == 4) {
          asm volatile("cp.async.bulk.wait_group 0;" ::: "memory");
          fence_async_all();
          flag_signal(&g_flags[32 + rb]);
        }
        mbar_wait(bar_empty + 8 * slot, ((kb >> 2) & 1) ^ 1);
        const uint32_t fb = bar_full + 8 * slot;
        const uint32_t dst = sbase + slot * P2_SLOT;
        mbar_expect_tx(fb, 40960);
        const CUtensorMap* tw = t < 5 ? &tm_wo : &tm_w2;
        const int kw = t < 5 ? kh * 320 + t * 64 : kact + (t - 5) * 64;
#pragma unroll
        for (int c = 0; c < 3; ++c) tma_load(dst + 16384 + c * 8192, tw, fb, ns * N2 + c * 64, kw);
        if (t == 0) { flag_wait(&g_flags[16 + rb], 8); fence_async_all(); }
        if (t == 5) { flag_wait(&g_flags[32 + rb], 8); fence_async_all(); }
        tma_load(dst, &tm_a2, fb, t < 5 ? kw : DM + kw, row0);
      }
    }
  } else {
    const int t = tid - 288;
    const int warp = t >> 5, lane = t & 31;
    {
      float gw[24];
      const uint4* gp = reinterpret_cast<const uint4*>(gate_w);
#pragma unroll
      for (int c = 0; c < 3; ++c) {
        uint4 v = make_uint4(0, 0, 0, 0);
        if (c < 2 || lane < 16) v = __ldg(gp + lane + 32 * c);
        gw[8 * c + 0] = bf_lo(v.x); gw[8 * c + 1] = bf_hi(v.x); gw[8 * c + 2] = bf_lo(v.y); gw[8 * c + 3] = bf_hi(v.y);
        gw[8 * c + 4] = bf_lo(v.z); gw[8 * c + 5] = bf_hi(v.z); gw[8 * c + 6] = bf_lo(v.w); gw[8 * c + 7] = bf_hi(v.w);
      }
#pragma unroll 1
      for (int r = warp * 4; r < 128; r += 12) {
        uint4 v[4][3];
#pragma unroll
        for (int u = 0; u < 4; ++u) {
          const uint4* xp = reinterpret_cast<const uint4*>(x + (size_t)(row0 + r + u) * DM);
#pragma unroll
          for (int c = 0; c < 3; ++c) {
            v[u][c] = make_uint4(0, 0, 0, 0);
            if (c < 2 || lane < 16) v[u][c] = __ldg(xp + lane + 32 * c);
          }
        }
#pragma unroll
        for (int u = 0; u < 4; ++u) {
          float s = 0.f;
#pragma unroll
          for (int c = 0; c < 3; ++c) {
            s += bf_lo(v[u][c].x) * gw[8 * c + 0] + bf_hi(v[u][c].x) * gw[8 * c + 1] + bf_lo(v[u][c].y) * gw[8 * c + 2] +
                 bf_hi(v[u][c].y) * gw[8 * c + 3] + bf_lo(v[u][c].z) * gw[8 * c + 4] + bf_hi(v[u][c].z) * gw[8 * c + 5] +
                 bf_lo(v[u][c].w) * gw[8 * c + 6] + bf_hi(v[u][c].w) * gw[8 * c + 7];
          }
#pragma unroll
          for (int o = 16; o > 0; o >>= 1) s += __shfl_xor_sync(0xffffffffu, s, o);
          if (lane == 0) g_s[r + u] = 1.f / (1.f + __expf(-s));
        }
      }
      mbar_arrive(bar_g);
    }
    if (t == 0) {
      mbar_wait(bar_stg, 0);
      tma_store(&tm_qkv_st, sbase, j * N1A, row0);
      asm volatile("cp.async.bulk.commit_group;" ::: "memory");
      asm volatile("cp.async.bulk.wait_group.read 0;" ::: "memory");
      mbar_arrive_cnt(bar_empty + 0, 2);
      mbar_arrive_cnt(bar_empty + 8, 2);
      asm volatile("cp.async.bulk.wait_group 0;" ::: "memory");
      fence_async_all();
      flag_signal(&g_flags[rb]);
      flag_wait(&g_flags[rb], 8);
      if (rb > 0) flag_wait(&g_flags[rb - 1], 8);
    }
    bar_sync(2, 96);
#pragma unroll 1
    for (int item = t; item < 128; item += 96) {
      const int h = item & 3, par = (item >> 2) & 1, grp = item >> 3;
      const int rq = grp * 8 + par;
      const size_t colq = (size_t)j * 80 + h * 20;
      float q[4][20];
#pragma unroll
      for (int u = 0; u < 4; ++u) {
        const uint2* p = reinterpret_cast<const uint2*>(g_qkv + (size_t)(row0 + rq + 2 * u) * NQKV + colq);
#pragma unroll
        for (int c = 0; c < 5; ++c) {
          const uint2 v = __ldcg(p + c);
          q[u][4 * c + 0] = bf_lo(v.x); q[u][4 * c + 1] = bf_hi(v.x); q[u][4 * c + 2] = bf_lo(v.y); q[u][4 * c + 3] = bf_hi(v.y);
        }
      }
      float lg[4][8];
#pragma unroll
      for (int m = 0; m < 11; ++m) {
        const int kr = row0 + rq + 2 * (m - 7);
        const uint2* p = reinterpret_cast<const uint2*>(g_qkv + (size_t)(kr < 0 ? 0 : kr) * NQKV + DM + colq);
        float kv[20];
#pragma unroll
        for (int c = 0; c < 5; ++c) {
          const uint2 v = __ldcg(p + c);
          kv[4 * c + 0] = bf_lo(v.x); kv[4 * c + 1] = bf_hi(v.x); kv[4 * c + 2] = bf_lo(v.y); kv[4 * c + 3] = bf_hi(v.y);
        }
#pragma unroll
        for (int u = 0; u < 4; ++u) {
          const int w = u - (m - 7);
          if (w >= 0 && w < 8) {
            float s = 0.f;
#pragma unroll
            for (int d = 0; d < 20; ++d) s = fmaf(q[u][d], kv[d], s);
            lg[u][w] = (kr < 0) ? -1e9f : s * 0.22360679774997896f;
          }
        }
      }
#pragma unroll
      for (int u = 0; u < 4; ++u) {
        float mx = lg[u][0];
#pragma unroll
        for (int w = 1; w < 8; ++w) mx = fmaxf(mx, lg[u][w]);
        float sum = 0.f;
#pragma unroll
        for (int w = 0; w < 8; ++w) { lg[u][w] = __expf(lg[u][w] - mx); sum += lg[u][w]; }
        const float sc = g_s[rq + 2 * u] / sum;
#pragma unroll
        for (int w = 0; w < 8; ++w) lg[u][w] *= sc;
      }
      float o[4][20];
#pragma unroll
      for (int u = 0; u < 4; ++u)
#pragma unroll
        for (int d = 0; d < 20; ++d) o[u][d] = 0.f;
#pragma unroll
      for (int m = 0; m < 11; ++m) {
        const int kr = row0 + rq + 2 * (m - 7);
        const uint2* p = reinterpret_cast<const uint2*>(g_qkv + (size_t)(kr < 0 ? 0 : kr) * NQKV + 2 * DM + colq);
        float kv[20];
#pragma unroll
        for (int c = 0; c < 5; ++c) {
          const uint2 v = __ldcg(p + c);
          kv[4 * c + 0] = bf_lo(v.x); kv[4 * c + 1] = bf_hi(v.x); kv[4 * c + 2] = bf_lo(v.y); kv[4 * c + 3] = bf_hi(v.y);
        }
#pragma unroll
        for (int u = 0; u < 4; ++u) {
          const int w = u - (m - 7);
          if (w >= 0 && w < 8) {
#pragma unroll
            for (int d = 0; d < 20; ++d) o[u][d] = fmaf(lg[u][w], kv[d], o[u][d]);
          }
        }
      }
#pragma unroll
      for (int u = 0; u < 4; ++u) {
        uint2* p = reinterpret_cast<uint2*>(g_a2 + (size_t)(row0 + rq + 2 * u) * KA2 + colq);
#pragma unroll
        for (int c = 0; c < 5; ++c)
          p[c] = make_uint2(pack_bf16(o[u][4 * c + 0], o[u][4 * c + 1]), pack_bf16(o[u][4 * c + 2], o[u][4 * c + 3]));
      }
    }
    __threadfence();
    fence_async_all();
    bar_sync(2, 96);
    if (t == 0) flag_signal(&g_flags[16 + rb]);
  }
}

typedef CUresult (*EncodeFn)(CUtensorMap*, CUtensorMapDataType, cuuint32_t, void*, const cuuint64_t*, const cuuint64_t*,
                             const cuuint32_t*, const cuuint32_t*, CUtensorMapInterleave, CUtensorMapSwizzle,
                             CUtensorMapL2promotion, CUtensorMapFloatOOBfill);

void make_map(EncodeFn enc, CUtensorMap* tm, const void* ptr, int rows, int cols, int box_rows, int box_cols, bool swizzle) {
  cuuint64_t gd[2] = {(cuuint64_t)cols, (cuuint64_t)rows};
  cuuint64_t gs[1] = {(cuuint64_t)cols * 2};
  cuuint32_t bx[2] = {(cuuint32_t)box_cols, (cuuint32_t)box_rows};
  cuuint32_t es[2] = {1, 1};
  enc(tm, CU_TENSOR_MAP_DATA_TYPE_BFLOAT16, 2, const_cast<void*>(ptr), gd, gs, bx, es, CU_TENSOR_MAP_INTERLEAVE_NONE,
      swizzle ? CU_TENSOR_MAP_SWIZZLE_128B : CU_TENSOR_MAP_SWIZZLE_NONE, CU_TENSOR_MAP_L2_PROMOTION_L2_128B,
      CU_TENSOR_MAP_FLOAT_OOB_FILL_NONE);
}

}

extern "C" void kernel_launch(void* const* d_in, const int* in_sizes, int n_in, void* d_out, int out_size) {
  const __nv_bfloat16* x = (const __nv_bfloat16*)d_in[0];
  const __nv_bfloat16* wqkv = (const __nv_bfloat16*)d_in[1];
  const __nv_bfloat16* wo = (const __nv_bfloat16*)d_in[2];
  const __nv_bfloat16* w1 = (const __nv_bfloat16*)d_in[4];
  const __nv_bfloat16* b1 = (const __nv_bfloat16*)d_in[5];
  const __nv_bfloat16* w2 = (const __nv_bfloat16*)d_in[6];
  const __nv_bfloat16* gate_w = (const __nv_bfloat16*)d_in[7];

  static EncodeFn enc = nullptr;
  static void* p_qkv = nullptr;
  static void* p_a2 = nullptr;
  if (!enc) {
    cudaDriverEntryPointQueryResult qr;
    cudaGetDriverEntryPoint("cuTensorMapEncodeTiled", (void**)&enc, cudaEnableDefault, &qr);
    cudaGetSymbolAddress(&p_qkv, g_qkv);
    cudaGetSymbolAddress(&p_a2, g_a2);
    cudaFuncSetAttribute(fused_kernel, cudaFuncAttributeMaxDynamicSharedMemorySize, SMEM_BYTES);
  }
  CUtensorMap tm_x, tm_wqkv, tm_w1, tm_a2, tm_wo, tm_w2, tm_qkv_st, tm_act_st;
  make_map(enc, &tm_x, x, SEQ, DM, 128, 64, true);
  make_map(enc, &tm_wqkv, wqkv, DM, NQKV, 64, 64, true);
  make_map(enc, &tm_w1, w1, DM, FF, 64, 64, true);
  make_map(enc, &tm_a2, p_a2, SEQ, KA2, 128, 64, true);
  make_map(enc, &tm_wo, wo, DM, DM, 64, 64, true);
  make_map(enc, &tm_w2, w2, FF, DM, 64, 64, true);
  make_map(enc, &tm_qkv_st, p_qkv, SEQ, NQKV, 128, N1A, false);
  make_map(enc, &tm_act_st, p_a2, SEQ, KA2, 128, N1B, false);
  fused_kernel<<<128, 384, SMEM_BYTES>>>(tm_x, tm_wqkv, tm_w1, tm_a2, tm_wo, tm_w2, tm_qkv_st, tm_act_st, x, b1, gate_w,
                                         (__nv_bfloat16*)d_out);
}
```

```cpp
#include <cuda_runtime.h>
#include <cuda_bf16.h>
#include <cuda.h>
#include <stdint.h>

namespace {

constexpr int SEQ = 2048, DM = 640, FF = 1728, NQKV = 1920, KA2 = 2368;
constexpr int NA = 224, NB = 240, N2 = 160;
constexpr int P1_SLOT = 49152;
constexpr int P2_SLOT = 40960;
constexpr int STG_OFF = 163840;
constexpr int STG_K = 20480, STG_V = 43520;
constexpr int PERM_OFF = 196608;
constexpr int GATE_OFF = 220160;
constexpr int CTRL_OFF = 230400;
constexpr int SMEM_BYTES = CTRL_OFF + 1152 + 896;
constexpr unsigned SPIN_LIMIT = 1u << 24;
constexpr int F_ACT = 0, F_O = 16, F_DONE = 32, F_WP = 40, F_PART = 64, F_HALO = 192, F_TOTAL = 320;

__device__ __align__(1024) __nv_bfloat16 g_a2[SEQ * KA2];
__device__ __align__(1024) __nv_bfloat16 g_wp[8 * DM * NB];
__device__ __align__(1024) float g_part[128 * 10240];
__device__ __align__(1024) uint8_t g_halo[128 * 5120];
__device__ unsigned int g_flags[F_TOTAL];

__device__ __forceinline__ uint32_t s32(const void* p) { return (uint32_t)__cvta_generic_to_shared(p); }
__device__ __forceinline__ void mbar_init(uint32_t b, uint32_t c) {
  asm volatile("mbarrier.init.shared::cta.b64 [%0], %1;" ::"r"(b), "r"(c) : "memory");
}
__device__ __forceinline__ void mbar_expect_tx(uint32_t b, uint32_t bytes) {
  asm volatile("mbarrier.arrive.expect_tx.shared::cta.b64 _, [%0], %1;" ::"r"(b), "r"(bytes) : "memory");
}
__device__ __forceinline__ void mbar_arrive(uint32_t b) {
  asm volatile("mbarrier.arrive.shared::cta.b64 _, [%0];" ::"r"(b) : "memory");
}
__device__ __forceinline__ void mbar_arrive_remote(uint32_t b) {
  asm volatile("mbarrier.arrive.shared::cluster.b64 _, [%0];" ::"r"(b) : "memory");
}
__device__ __forceinline__ void mbar_wait(uint32_t b, uint32_t parity) {
  uint32_t ok = 0;
  for (unsigned it = 0; it < SPIN_LIMIT && !ok; ++it) {
    asm volatile("{\n.reg .pred p;\nmbarrier.try_wait.parity.shared::cta.b64 p, [%1], %2;\nselp.u32 %0, 1, 0, p;\n}"
                 : "=r"(ok) : "r"(b), "r"(parity) : "memory");
  }
}
__device__ __forceinline__ void tma_load(uint32_t dst, const CUtensorMap* tm, uint32_t bar, int c0, int c1) {
  asm volatile("cp.async.bulk.tensor.2d.shared::cluster.global.mbarrier::complete_tx::bytes [%0], [%1, {%3, %4}], [%2];"
               ::"r"(dst), "l"(tm), "r"(bar), "r"(c0), "r"(c1) : "memory");
}
__device__ __forceinline__ void tma_load_mc(uint32_t dst, const CUtensorMap* tm, uint32_t bar, int c0, int c1) {
  asm volatile("cp.async.bulk.tensor.2d.shared::cluster.global.mbarrier::complete_tx::bytes.multicast::cluster [%0], [%1, {%3, %4}], [%2], %5;"
               ::"r"(dst), "l"(tm), "r"(bar), "r"(c0), "r"(c1), "h"((uint16_t)3) : "memory");
}
__device__ __forceinline__ void tma_store3(const CUtensorMap* tm, uint32_t src, int c0, int c1, int c2) {
  asm volatile("cp.async.bulk.tensor.3d.global.shared::cta.bulk_group [%0, {%2, %3, %4}], [%1];"
               ::"l"(tm), "r"(src), "r"(c0), "r"(c1), "r"(c2) : "memory");
}
__device__ __forceinline__ void tma_store(const CUtensorMap* tm, uint32_t src, int c0, int c1) {
  asm volatile("cp.async.bulk.tensor.2d.global.shared::cta.bulk_group [%0, {%2, %3}], [%1];"
               ::"l"(tm), "r"(src), "r"(c0), "r"(c1) : "memory");
}
__device__ __forceinline__ void bulk_store(void* gdst, uint32_t src, uint32_t bytes) {
  asm volatile("cp.async.bulk.global.shared::cta.bulk_group [%0], [%1], %2;" ::"l"(gdst), "r"(src), "r"(bytes) : "memory");
}
__device__ __forceinline__ void bulk_load(uint32_t dst, const void* gsrc, uint32_t bytes, uint32_t bar) {
  asm volatile("cp.async.bulk.shared::cluster.global.mbarrier::complete_tx::bytes [%0], [%1], %2, [%3];"
               ::"r"(dst), "l"(gsrc), "r"(bytes), "r"(bar) : "memory");
}
__device__ __forceinline__ void bulk_commit() { asm volatile("cp.async.bulk.commit_group;" ::: "memory"); }
__device__ __forceinline__ void bulk_wait_read() { asm volatile("cp.async.bulk.wait_group.read 0;" ::: "memory"); }
__device__ __forceinline__ void bulk_wait_all() { asm volatile("cp.async.bulk.wait_group 0;" ::: "memory"); }
__device__ __forceinline__ void prefetch_tmap(const CUtensorMap* tm) {
  asm volatile("prefetch.tensormap [%0];" ::"l"(tm) : "memory");
}
__device__ __forceinline__ void wgmma_fence() { asm volatile("wgmma.fence.sync.aligned;" ::: "memory"); }
__device__ __forceinline__ void wgmma_commit() { asm volatile("wgmma.commit_group.sync.aligned;" ::: "memory"); }
template <int N> __device__ __forceinline__ void wgmma_wait() { asm volatile("wgmma.wait_group.sync.aligned %0;" ::"n"(N) : "memory"); }
__device__ __forceinline__ void bar_sync(int id, int n) { asm volatile("bar.sync %0, %1;" ::"r"(id), "r"(n) : "memory"); }
__device__ __forceinline__ void fence_async_smem() { asm volatile("fence.proxy.async.shared::cta;" ::: "memory"); }
__device__ __forceinline__ void flag_signal(unsigned int* f) {
  asm volatile("red.relaxed.gpu.global.add.u32 [%0], 1;" ::"l"(f) : "memory");
}
__device__ __forceinline__ void flag_wait(const unsigned int* f, unsigned int target) {
  unsigned int v = 0;
  for (unsigned it = 0; it < SPIN_LIMIT; ++it) {
    asm volatile("ld.relaxed.gpu.global.u32 %0, [%1];" : "=r"(v) : "l"(f) : "memory");
    if (v >= target) break;
    __nanosleep(40);
  }
}
__device__ __forceinline__ uint64_t desc_a(uint32_t addr) {
  return (uint64_t)((addr & 0x3FFFF) >> 4) | ((uint64_t)1 << 16) | ((uint64_t)64 << 32) | ((uint64_t)1 << 62);
}
__device__ __forceinline__ uint64_t desc_b128(uint32_t addr) {
  return (uint64_t)((addr & 0x3FFFF) >> 4) | ((uint64_t)512 << 16) | ((uint64_t)64 << 32) | ((uint64_t)1 << 62);
}
__device__ __forceinline__ uint64_t desc_gate(uint32_t addr) {
  return (uint64_t)((addr & 0x3FFFF) >> 4) | ((uint64_t)8 << 16) | ((uint64_t)8 << 32);
}
__device__ __forceinline__ void wgmma_gate(float (&d)[4], uint64_t da, uint64_t db, int scale_d) {
  asm volatile("{\n.reg .pred p;\nsetp.ne.b32 p, %6, 0;\n"
               "wgmma.mma_async.sync.aligned.m64n8k16.f32.bf16.bf16 {%0, %1, %2, %3}, %4, %5, p, 1, 1, 0, 0;\n}\n"
               : "+f"(d[0]), "+f"(d[1]), "+f"(d[2]), "+f"(d[3]) : "l"(da), "l"(db), "r"(scale_d));
}
__device__ __forceinline__ uint32_t pack_bf16(float lo, float hi) {
  __nv_bfloat162 v = __floats2bfloat162_rn(lo, hi);
  return *reinterpret_cast<uint32_t*>(&v);
}
__device__ __forceinline__ void stsm_x4(uint32_t addr, uint32_t r0, uint32_t r1, uint32_t r2, uint32_t r3) {
  asm volatile("stmatrix.sync.aligned.m8n8.x4.shared.b16 [%0], {%1, %2, %3, %4};" ::"r"(addr), "r"(r0), "r"(r1), "r"(r2), "r"(r3) : "memory");
}
__device__ __forceinline__ float bf_lo(uint32_t v) { return __uint_as_float(v << 16); }
__device__ __forceinline__ float bf_hi(uint32_t v) { return __uint_as_float(v & 0xFFFF0000u); }
__device__ __forceinline__ float ex2(float x) { float y; asm("ex2.approx.ftz.f32 %0, %1;" : "=f"(y) : "f"(x)); return y; }
__device__ __forceinline__ float rcp(float x) { float y; asm("rcp.approx.ftz.f32 %0, %1;" : "=f"(y) : "f"(x)); return y; }
constexpr float LOG2E = 1.4426950408889634f;

__device__ __forceinline__ uint32_t mish2_pack(float h0, float h1, float s) {
  const float e0 = ex2(fminf(h0, 20.f) * LOG2E), e1 = ex2(fminf(h1, 20.f) * LOG2E);
  const float u0 = fmaf(e0, e0 + 2.f, 2.f), u1 = fmaf(e1, e1 + 2.f, 2.f);
  const float r = (-2.f * s) * rcp(u0 * u1);
  return pack_bf16(h0 * fmaf(r, u1, s), h1 * fmaf(r, u0, s));
}

__device__ __forceinline__ void wgmma_n240(float (&d)[120], uint64_t da, uint64_t db, int scale_d) {
  asm volatile("{\n.reg .pred p;\nsetp.ne.b32 p, %122, 0;\n"
    "wgmma.mma_async.sync.aligned.m64n240k16.f32.bf16.bf16 {%0, %1, %2, %3, %4, %5, %6, %7, %8, %9, %10, %11, %12, %13, %14, %15, %16, %17, %18, %19, %20, %21, %22, %23, %24, %25, %26, %27, %28, %29, %30, %31, %32, %33, %34, %35, %36, %37, %38, %39, %40, %41, %42, %43, %44, %45, %46, %47, %48, %49, %50, %51, %52, %53, %54, %55, %56, %57, %58, %59, %60, %61, %62, %63, %64, %65, %66, %67, %68, %69, %70, %71, %72, %73, %74, %75, %76, %77, %78, %79, %80, %81, %82, %83, %84, %85, %86, %87, %88, %89, %90, %91, %92, %93, %94, %95, %96, %97, %98, %99, %100, %101, %102, %103, %104, %105, %106, %107, %108, %109, %110, %111, %112, %113, %114, %115, %116, %117, %118, %119}, %120, %121, p, 1, 1, 0, 1;\n}\n"
    : "+f"(d[0]), "+f"(d[1]), "+f"(d[2]), "+f"(d[3]), "+f"(d[4]), "+f"(d[5]), "+f"(d[6]), "+f"(d[7]), "+f"(d[8]), "+f"(d[9]), "+f"(d[10]), "+f"(d[11]), "+f"(d[12]), "+f"(d[13]), "+f"(d[14]), "+f"(d[15]), "+f"(d[16]), "+f"(d[17]), "+f"(d[18]), "+f"(d[19]), "+f"(d[20]), "+f"(d[21]), "+f"(d[22]), "+f"(d[23]), "+f"(d[24]), "+f"(d[25]), "+f"(d[26]), "+f"(d[27]), "+f"(d[28]), "+f"(d[29]), "+f"(d[30]), "+f"(d[31]), "+f"(d[32]), "+f"(d[33]), "+f"(d[34]), "+f"(d[35]), "+f"(d[36]), "+f"(d[37]), "+f"(d[38]), "+f"(d[39]), "+f"(d[40]), "+f"(d[41]), "+f"(d[42]), "+f"(d[43]), "+f"(d[44]), "+f"(d[45]), "+f"(d[46]), "+f"(d[47]), "+f"(d[48]), "+f"(d[49]), "+f"(d[50]), "+f"(d[51]), "+f"(d[52]), "+f"(d[53]), "+f"(d[54]), "+f"(d[55]), "+f"(d[56]), "+f"(d[57]), "+f"(d[58]), "+f"(d[59]), "+f"(d[60]), "+f"(d[61]), "+f"(d[62]), "+f"(d[63]), "+f"(d[64]), "+f"(d[65]), "+f"(d[66]), "+f"(d[67]), "+f"(d[68]), "+f"(d[69]), "+f"(d[70]), "+f"(d[71]), "+f"(d[72]), "+f"(d[73]), "+f"(d[74]), "+f"(d[75]), "+f"(d[76]), "+f"(d[77]), "+f"(d[78]), "+f"(d[79]), "+f"(d[80]), "+f"(d[81]), "+f"(d[82]), "+f"(d[83]), "+f"(d[84]), "+f"(d[85]), "+f"(d[86]), "+f"(d[87]), "+f"(d[88]), "+f"(d[89]), "+f"(d[90]), "+f"(d[91]), "+f"(d[92]), "+f"(d[93]), "+f"(d[94]), "+f"(d[95]), "+f"(d[96]), "+f"(d[97]), "+f"(d[98]), "+f"(d[99]), "+f"(d[100]), "+f"(d[101]), "+f"(d[102]), "+f"(d[103]), "+f"(d[104]), "+f"(d[105]), "+f"(d[106]), "+f"(d[107]), "+f"(d[108]), "+f"(d[109]), "+f"(d[110]), "+f"(d[111]), "+f"(d[112]), "+f"(d[113]), "+f"(d[114]), "+f"(d[115]), "+f"(d[116]), "+f"(d[117]), "+f"(d[118]), "+f"(d[119])
    : "l"(da), "l"(db), "r"(scale_d));
}

__device__ __forceinline__ void wgmma_n224(float (&d)[112], uint64_t da, uint64_t db, int scale_d) {
  asm volatile("{\n.reg .pred p;\nsetp.ne.b32 p, %114, 0;\n"
    "wgmma.mma_async.sync.aligned.m64n224k16.f32.bf16.bf16 {%0, %1, %2, %3, %4, %5, %6, %7, %8, %9, %10, %11, %12, %13, %14, %15, %16, %17, %18, %19, %20, %21, %22, %23, %24, %25, %26, %27, %28, %29, %30, %31, %32, %33, %34, %35, %36, %37, %38, %39, %40, %41, %42, %43, %44, %45, %46, %47, %48, %49, %50, %51, %52, %53, %54, %55, %56, %57, %58, %59, %60, %61, %62, %63, %64, %65, %66, %67, %68, %69, %70, %71, %72, %73, %74, %75, %76, %77, %78, %79, %80, %81, %82, %83, %84, %85, %86, %87, %88, %89, %90, %91, %92, %93, %94, %95, %96, %97, %98, %99, %100, %101, %102, %103, %104, %105, %106, %107, %108, %109, %110, %111}, %112, %113, p, 1, 1, 0, 1;\n}\n"
    : "+f"(d[0]), "+f"(d[1]), "+f"(d[2]), "+f"(d[3]), "+f"(d[4]), "+f"(d[5]), "+f"(d[6]), "+f"(d[7]), "+f"(d[8]), "+f"(d[9]), "+f"(d[10]), "+f"(d[11]), "+f"(d[12]), "+f"(d[13]), "+f"(d[14]), "+f"(d[15]), "+f"(d[16]), "+f"(d[17]), "+f"(d[18]), "+f"(d[19]), "+f"(d[20]), "+f"(d[21]), "+f"(d[22]), "+f"(d[23]), "+f"(d[24]), "+f"(d[25]), "+f"(d[26]), "+f"(d[27]), "+f"(d[28]), "+f"(d[29]), "+f"(d[30]), "+f"(d[31]), "+f"(d[32]), "+f"(d[33]), "+f"(d[34]), "+f"(d[35]), "+f"(d[36]), "+f"(d[37]), "+f"(d[38]), "+f"(d[39]), "+f"(d[40]), "+f"(d[41]), "+f"(d[42]), "+f"(d[43]), "+f"(d[44]), "+f"(d[45]), "+f"(d[46]), "+f"(d[47]), "+f"(d[48]), "+f"(d[49]), "+f"(d[50]), "+f"(d[51]), "+f"(d[52]), "+f"(d[53]), "+f"(d[54]), "+f"(d[55]), "+f"(d[56]), "+f"(d[57]), "+f"(d[58]), "+f"(d[59]), "+f"(d[60]), "+f"(d[61]), "+f"(d[62]), "+f"(d[63]), "+f"(d[64]), "+f"(d[65]), "+f"(d[66]), "+f"(d[67]), "+f"(d[68]), "+f"(d[69]), "+f"(d[70]), "+f"(d[71]), "+f"(d[72]), "+f"(d[73]), "+f"(d[74]), "+f"(d[75]), "+f"(d[76]), "+f"(d[77]), "+f"(d[78]), "+f"(d[79]), "+f"(d[80]), "+f"(d[81]), "+f"(d[82]), "+f"(d[83]), "+f"(d[84]), "+f"(d[85]), "+f"(d[86]), "+f"(d[87]), "+f"(d[88]), "+f"(d[89]), "+f"(d[90]), "+f"(d[91]), "+f"(d[92]), "+f"(d[93]), "+f"(d[94]), "+f"(d[95]), "+f"(d[96]), "+f"(d[97]), "+f"(d[98]), "+f"(d[99]), "+f"(d[100]), "+f"(d[101]), "+f"(d[102]), "+f"(d[103]), "+f"(d[104]), "+f"(d[105]), "+f"(d[106]), "+f"(d[107]), "+f"(d[108]), "+f"(d[109]), "+f"(d[110]), "+f"(d[111])
    : "l"(da), "l"(db), "r"(scale_d));
}

__device__ __forceinline__ void wgmma_n160(float (&d)[80], uint64_t da, uint64_t db, int scale_d) {
  asm volatile("{\n.reg .pred p;\nsetp.ne.b32 p, %82, 0;\n"
    "wgmma.mma_async.sync.aligned.m64n160k16.f32.bf16.bf16 {%0, %1, %2, %3, %4, %5, %6, %7, %8, %9, %10, %11, %12, %13, %14, %15, %16, %17, %18, %19, %20, %21, %22, %23, %24, %25, %26, %27, %28, %29, %30, %31, %32, %33, %34, %35, %36, %37, %38, %39, %40, %41, %42, %43, %44, %45, %46, %47, %48, %49, %50, %51, %52, %53, %54, %55, %56, %57, %58, %59, %60, %61, %62, %63, %64, %65, %66, %67, %68, %69, %70, %71, %72, %73, %74, %75, %76, %77, %78, %79}, %80, %81, p, 1, 1, 0, 1;\n}\n"
    : "+f"(d[0]), "+f"(d[1]), "+f"(d[2]), "+f"(d[3]), "+f"(d[4]), "+f"(d[5]), "+f"(d[6]), "+f"(d[7]), "+f"(d[8]), "+f"(d[9]), "+f"(d[10]), "+f"(d[11]), "+f"(d[12]), "+f"(d[13]), "+f"(d[14]), "+f"(d[15]), "+f"(d[16]), "+f"(d[17]), "+f"(d[18]), "+f"(d[19]), "+f"(d[20]), "+f"(d[21]), "+f"(d[22]), "+f"(d[23]), "+f"(d[24]), "+f"(d[25]), "+f"(d[26]), "+f"(d[27]), "+f"(d[28]), "+f"(d[29]), "+f"(d[30]), "+f"(d[31]), "+f"(d[32]), "+f"(d[33]), "+f"(d[34]), "+f"(d[35]), "+f"(d[36]), "+f"(d[37]), "+f"(d[38]), "+f"(d[39]), "+f"(d[40]), "+f"(d[41]), "+f"(d[42]), "+f"(d[43]), "+f"(d[44]), "+f"(d[45]), "+f"(d[46]), "+f"(d[47]), "+f"(d[48]), "+f"(d[49]), "+f"(d[50]), "+f"(d[51]), "+f"(d[52]), "+f"(d[53]), "+f"(d[54]), "+f"(d[55]), "+f"(d[56]), "+f"(d[57]), "+f"(d[58]), "+f"(d[59]), "+f"(d[60]), "+f"(d[61]), "+f"(d[62]), "+f"(d[63]), "+f"(d[64]), "+f"(d[65]), "+f"(d[66]), "+f"(d[67]), "+f"(d[68]), "+f"(d[69]), "+f"(d[70]), "+f"(d[71]), "+f"(d[72]), "+f"(d[73]), "+f"(d[74]), "+f"(d[75]), "+f"(d[76]), "+f"(d[77]), "+f"(d[78]), "+f"(d[79])
    : "l"(da), "l"(db), "r"(scale_d));
}


__global__ void __cluster_dims__(2, 1, 1) __launch_bounds__(384, 1)
fused_kernel(const __grid_constant__ CUtensorMap tm_x, const __grid_constant__ CUtensorMap tm_wqkv,
             const __grid_constant__ CUtensorMap tm_w1, const __grid_constant__ CUtensorMap tm_a2,
             const __grid_constant__ CUtensorMap tm_wo, const __grid_constant__ CUtensorMap tm_w2,
             const __grid_constant__ CUtensorMap tm_act_st, const __grid_constant__ CUtensorMap tm_o_st,
             const __grid_constant__ CUtensorMap tm_wp_st, const __grid_constant__ CUtensorMap tm_wp,
             const __nv_bfloat16* __restrict__ b1, const __nv_bfloat16* __restrict__ gate_w,
             __nv_bfloat16* __restrict__ out) {
  extern __shared__ uint8_t smem_raw[];
  const uint32_t sbase = (s32(smem_raw) + 1023u) & ~1023u;
  uint8_t* sgen = smem_raw + (sbase - s32(smem_raw));
  const uint32_t bar_full1 = sbase + CTRL_OFF;
  const uint32_t bar_empty1 = bar_full1 + 32;
  const uint32_t bar_full2 = bar_full1 + 64;
  const uint32_t bar_empty2 = bar_full1 + 96;
  const uint32_t bar_gw = bar_full1 + 128;
  const uint32_t bar_act = bar_full1 + 136;
  const uint32_t bar_free = bar_full1 + 152;
  const uint32_t bar_dump = bar_full1 + 160;
  const uint32_t bar_halo = bar_full1 + 168;
  const uint32_t bar_o = bar_full1 + 176;
  const uint32_t bar_perm = bar_full1 + 184;
  float* g_s = reinterpret_cast<float*>(sgen + CTRL_OFF + 192);
  uint8_t* bias_s = sgen + CTRL_OFF + 704;

  const int tid = threadIdx.x;
  const int cm = blockIdx.x & 1;
  const int j = (blockIdx.x >> 1) & 7;
  const int rb = (blockIdx.x >> 4) * 2 + cm;
  const int ns = j >> 1, kh = j & 1;
  const int row0 = rb * 128;
  const int c1 = 432 * (j >> 1) + 208 * (j & 1);
  const int nkb = kh ? 18 : 19;

  if (tid == 0) {
    for (int s = 0; s < 4; ++s) { mbar_init(bar_full1 + 8 * s, 1); mbar_init(bar_empty1 + 8 * s, 4); }
    for (int s = 0; s < 4; ++s) { mbar_init(bar_full2 + 8 * s, 1); mbar_init(bar_empty2 + 8 * s, 4); }
    mbar_init(bar_gw, 96);
    mbar_init(bar_act, 128);
    mbar_init(bar_act + 8, 128);
    mbar_init(bar_free, 1);
    mbar_init(bar_dump, 256);
    mbar_init(bar_halo, 1);
    mbar_init(bar_o, 256);
    mbar_init(bar_perm, 1);
    asm volatile("fence.mbarrier_init.release.cluster;" ::: "memory");
  }
  __syncthreads();
  asm volatile("barrier.cluster.arrive.release.aligned;\nbarrier.cluster.wait.acquire.aligned;" ::: "memory");

  uint32_t peer_ctrl;
  asm volatile("mapa.shared::cluster.u32 %0, %1, %2;" : "=r"(peer_ctrl) : "r"(bar_full1), "r"(cm ^ 1));
  const int wg = tid >> 7;
  if (wg < 2) {
    const int warp = (tid >> 5) & 3, lane = tid & 31;
    const bool elected = (tid & 127) == 0;
    const int st_row = wg * 64 + warp * 16 + (lane & 7) + ((lane >> 3) & 1) * 8;
    const int st_col = (lane >> 4) * 16;
    {
      float acc[NA / 2];
      float gz[4];
      mbar_wait(bar_gw, 0);
#pragma unroll 1
      for (int kb = 0; kb < 10; ++kb) {
        const int slot = kb & 3;
        mbar_wait(bar_full1 + 8 * slot, (kb >> 2) & 1);
        const uint32_t a0 = sbase + slot * P1_SLOT + wg * 8192;
        const uint32_t b0 = sbase + slot * P1_SLOT + 16384;
        const uint32_t w0 = sbase + GATE_OFF + kb * 1024;
        wgmma_fence();
#pragma unroll
        for (int k = 0; k < 4; ++k) {
          wgmma_n224(acc, desc_a(a0 + k * 32), desc_b128(b0 + k * 2048), (kb | k) != 0);
          wgmma_gate(gz, desc_a(a0 + k * 32), desc_gate(w0 + k * 256), (kb | k) != 0);
        }
        wgmma_commit();
        if (kb > 0) {
          wgmma_wait<1>();
          if (elected) { const int ps = (kb - 1) & 3; mbar_arrive(bar_empty1 + 8 * ps); mbar_arrive_remote(peer_ctrl + 32 + 8 * ps); }
        }
      }
      wgmma_wait<0>();
      if (elected) { mbar_arrive(bar_empty1 + 8); mbar_arrive_remote(peer_ctrl + 32 + 8); }
      if ((lane & 3) == 0) {
        g_s[wg * 64 + warp * 16 + (lane >> 2)] = rcp(1.f + ex2(-gz[0] * LOG2E));
        g_s[wg * 64 + warp * 16 + (lane >> 2) + 8] = rcp(1.f + ex2(-gz[2] * LOG2E));
      }
      mbar_wait(bar_free, 0);
      bar_sync(1, 256);
      const uint32_t stg = sbase + STG_OFF + st_row * (NA * 2) + st_col;
#pragma unroll
      for (int q = 0; q < 14; ++q) {
        stsm_x4(stg + q * 32, pack_bf16(acc[8 * q + 0], acc[8 * q + 1]), pack_bf16(acc[8 * q + 2], acc[8 * q + 3]),
                pack_bf16(acc[8 * q + 4], acc[8 * q + 5]), pack_bf16(acc[8 * q + 6], acc[8 * q + 7]));
      }
      __syncwarp();
    }
    {
      float acc[NB / 2];
      uint8_t* mbase = sgen + STG_OFF + (wg * 64 + warp * 16) * (NA * 2);
      const float* gr = g_s + wg * 64 + warp * 16;
      int mr = lane / 28, mc = lane - mr * 28;
      int slot = 2, n3 = 0, prev = 0;
#pragma unroll 1
      for (int i = 0; i < 10; ++i) {
        mbar_wait(bar_full1 + 8 * slot, ((slot == 2 ? 2 : 3) + n3) & 1);
        const uint32_t a0 = sbase + slot * P1_SLOT + wg * 8192;
        const uint32_t b0 = sbase + slot * P1_SLOT + 16384;
        wgmma_fence();
#pragma unroll
        for (int k = 0; k < 4; ++k) wgmma_n240(acc, desc_a(a0 + k * 32), desc_b128(b0 + k * 2048), (i | k) != 0);
        wgmma_commit();
        if (i > 0) {
          wgmma_wait<1>();
          if (elected) { mbar_arrive(bar_empty1 + 8 * prev); mbar_arrive_remote(peer_ctrl + 32 + 8 * prev); }
        }
        prev = slot;
        if (slot == 1) { slot = 2; ++n3; } else { slot = slot == 2 ? 0 : 1; }
        if (i < 7) {
          uint4* p0 = reinterpret_cast<uint4*>(mbase + (i * 32 + lane) * 16);
          uint4* p1 = p0 + 224;
          const uint4 h0 = *p0, h1 = *p1;
          const uint4 bv = *reinterpret_cast<const uint4*>(bias_s + mc * 16);
          const float om0 = 1.f - gr[mr], om1 = 1.f - gr[mr + 8];
          uint4 o0, o1;
          o0.x = mish2_pack(bf_lo(h0.x) + bf_lo(bv.x), bf_hi(h0.x) + bf_hi(bv.x), om0);
          o1.x = mish2_pack(bf_lo(h1.x) + bf_lo(bv.x), bf_hi(h1.x) + bf_hi(bv.x), om1);
          o0.y = mish2_pack(bf_lo(h0.y) + bf_lo(bv.y), bf_hi(h0.y) + bf_hi(bv.y), om0);
          o1.y = mish2_pack(bf_lo(h1.y) + bf_lo(bv.y), bf_hi(h1.y) + bf_hi(bv.y), om1);
          o0.z = mish2_pack(bf_lo(h0.z) + bf_lo(bv.z), bf_hi(h0.z) + bf_hi(bv.z), om0);
          o1.z = mish2_pack(bf_lo(h1.z) + bf_lo(bv.z), bf_hi(h1.z) + bf_hi(bv.z), om1);
          o0.w = mish2_pack(bf_lo(h0.w) + bf_lo(bv.w), bf_hi(h0.w) + bf_hi(bv.w), om0);
          o1.w = mish2_pack(bf_lo(h1.w) + bf_lo(bv.w), bf_hi(h1.w) + bf_hi(bv.w), om1);
          *p0 = o0; *p1 = o1;
          mc += 4; mr += 1;
          if (mc >= 28) { mc -= 28; mr += 1; }
          if (i == 6) {
            fence_async_smem();
            mbar_arrive(bar_act + 8 * wg);
          }
        }
      }
      wgmma_wait<0>();
      if (elected) { mbar_arrive(bar_empty1 + 16); mbar_arrive_remote(peer_ctrl + 32 + 16); }
      mbar_wait(bar_free, 1);
      const uint32_t stg = sbase + STG_OFF + st_row * 160 + st_col;
#pragma unroll
      for (int q = 0; q < 15; ++q) {
        const uint32_t off = (q / 5 == 0 ? 0 : (q / 5 == 1 ? STG_K + 2560 : STG_V + 2560)) + (q % 5) * 32;
        stsm_x4(stg + off, pack_bf16(acc[8 * q + 0], acc[8 * q + 1]), pack_bf16(acc[8 * q + 2], acc[8 * q + 3]),
                pack_bf16(acc[8 * q + 4], acc[8 * q + 5]), pack_bf16(acc[8 * q + 6], acc[8 * q + 7]));
      }
      if (rb == 0 && tid < 160) {
        *reinterpret_cast<uint4*>(sgen + STG_OFF + STG_K + tid * 16) = make_uint4(0, 0, 0, 0);
        *reinterpret_cast<uint4*>(sgen + STG_OFF + STG_V + tid * 16) = make_uint4(0, 0, 0, 0);
      }
      fence_async_smem();
      mbar_arrive(bar_dump);
      bar_sync(1, 256);
    }
    {
      float acc[N2 / 2];
      auto step = [&](int t) {
        const int slot = t & 3;
        mbar_wait(bar_full2 + 8 * slot, (t >> 2) & 1);
        const uint32_t a0 = sbase + slot * P2_SLOT + wg * 8192;
        const uint32_t b0 = sbase + slot * P2_SLOT + 16384;
        wgmma_fence();
#pragma unroll
        for (int k = 0; k < 4; ++k) wgmma_n160(acc, desc_a(a0 + k * 32), desc_b128(b0 + k * 2048), (t | k) != 0);
        wgmma_commit();
        if (t > 0) {
          wgmma_wait<1>();
          if (elected && t + 3 < nkb) { const int ps = (t - 1) & 3; mbar_arrive(bar_empty2 + 8 * ps); mbar_arrive_remote(peer_ctrl + 96 + 8 * ps); }
        }
      };
#pragma unroll 1
      for (int u = 0; u < 2; ++u) {
        const int qi = (1 - u) * 256 + tid;
        const int row = qi >> 2;
        uint8_t* qs = sgen + STG_OFF + qi * 40;
        const uint8_t* ks = qs + STG_K + 2560;
        const uint8_t* vs = qs + STG_V + 2560;
        float q[20], lg[8], o[20];
        step(4 * u);
        if (u == 1) mbar_wait(bar_halo, 0);
#pragma unroll
        for (int c = 0; c < 5; ++c) {
          const uint2 v = *reinterpret_cast<const uint2*>(qs + c * 8);
          q[4 * c + 0] = bf_lo(v.x); q[4 * c + 1] = bf_hi(v.x); q[4 * c + 2] = bf_lo(v.y); q[4 * c + 3] = bf_hi(v.y);
        }
#pragma unroll
        for (int w = 0; w < 8; ++w) {
          if (w == 4) step(4 * u + 1);
          float s0 = 0.f, s1 = 0.f;
#pragma unroll
          for (int c = 0; c < 5; ++c) {
            const uint2 v = *reinterpret_cast<const uint2*>(ks - w * 320 + c * 8);
            s0 = fmaf(q[4 * c + 0], bf_lo(v.x), s0); s1 = fmaf(q[4 * c + 1], bf_hi(v.x), s1);
            s0 = fmaf(q[4 * c + 2], bf_lo(v.y), s0); s1 = fmaf(q[4 * c + 3], bf_hi(v.y), s1);
          }
          lg[w] = (row0 + row - 2 * w >= 0) ? (s0 + s1) * (0.22360679774997896f * LOG2E) : -1e9f;
        }
        float mx = lg[0];
#pragma unroll
        for (int w = 1; w < 8; ++w) mx = fmaxf(mx, lg[w]);
        float sum = 0.f;
#pragma unroll
        for (int w = 0; w < 8; ++w) { lg[w] = ex2(lg[w] - mx); sum += lg[w]; }
        const float sc = g_s[row] * rcp(sum);
#pragma unroll
        for (int d = 0; d < 20; ++d) o[d] = 0.f;
#pragma unroll
        for (int w = 0; w < 8; ++w) {
          if (w == 0) step(4 * u + 2);
          if (w == 4) step(4 * u + 3);
          const float p = lg[w] * sc;
#pragma unroll
          for (int c = 0; c < 5; ++c) {
            const uint2 v = *reinterpret_cast<const uint2*>(vs - w * 320 + c * 8);
            o[4 * c + 0] = fmaf(p, bf_lo(v.x), o[4 * c + 0]); o[4 * c + 1] = fmaf(p, bf_hi(v.x), o[4 * c + 1]);
            o[4 * c + 2] = fmaf(p, bf_lo(v.y), o[4 * c + 2]); o[4 * c + 3] = fmaf(p, bf_hi(v.y), o[4 * c + 3]);
          }
        }
#pragma unroll
        for (int c = 0; c < 5; ++c)
          *reinterpret_cast<uint2*>(qs + c * 8) =
              make_uint2(pack_bf16(o[4 * c + 0], o[4 * c + 1]), pack_bf16(o[4 * c + 2], o[4 * c + 3]));
      }
      fence_async_smem();
      mbar_arrive(bar_o);
#pragma unroll 1
      for (int t = 8; t < nkb; ++t) {
        step(t);
      }
      wgmma_wait<0>();
#pragma unroll
      for (int q = 0; q < 10; ++q) {
        *reinterpret_cast<float4*>(sgen + STG_OFF + 20480 + q * 4096 + tid * 16) =
            kh ? make_float4(acc[4 * q + 0], acc[4 * q + 1], acc[4 * q + 2], acc[4 * q + 3])
               : make_float4(acc[40 + 4 * q + 0], acc[40 + 4 * q + 1], acc[40 + 4 * q + 2], acc[40 + 4 * q + 3]);
      }
      fence_async_smem();
      bar_sync(1, 256);
      const int partner = blockIdx.x ^ 2;
      if (tid == 0) {
        bulk_store(g_part + (size_t)blockIdx.x * 10240, sbase + STG_OFF + 20480, 40960);
        bulk_commit();
        bulk_wait_all();
        flag_signal(&g_flags[F_PART + blockIdx.x]);
        flag_wait(&g_flags[F_PART + partner], 1);
      }
      bar_sync(1, 256);
      const float4* pp = reinterpret_cast<const float4*>(g_part + (size_t)partner * 10240) + tid;
      float4 pv[10];
#pragma unroll
      for (int q = 0; q < 10; ++q) pv[q] = __ldcg(pp + q * 256);
      const int r_lo = row0 + wg * 64 + warp * 16 + (lane >> 2);
      __nv_bfloat16* o0 = out + (size_t)r_lo * DM + ns * N2 + kh * 80 + (lane & 3) * 2;
      __nv_bfloat16* o1 = o0 + 8 * DM;
#pragma unroll
      for (int q = 0; q < 10; ++q) {
        const float v0 = (kh ? acc[40 + 4 * q + 0] : acc[4 * q + 0]) + pv[q].x;
        const float v1 = (kh ? acc[40 + 4 * q + 1] : acc[4 * q + 1]) + pv[q].y;
        const float v2 = (kh ? acc[40 + 4 * q + 2] : acc[4 * q + 2]) + pv[q].z;
        const float v3 = (kh ? acc[40 + 4 * q + 3] : acc[4 * q + 3]) + pv[q].w;
        *reinterpret_cast<uint32_t*>(o0 + q * 8) = pack_bf16(v0, v1);
        *reinterpret_cast<uint32_t*>(o1 + q * 8) = pack_bf16(v2, v3);
      }
      if (tid == 0) {
        const unsigned int prev = atomicInc(&g_flags[F_DONE], gridDim.x - 1);
        if (prev == gridDim.x - 1) {
          for (int f = 0; f < F_TOTAL; ++f)
            if (f != F_DONE) g_flags[f] = 0;
        }
      }
    }
  } else if (tid < 288) {
    if (tid == 256) {
      prefetch_tmap(&tm_x); prefetch_tmap(&tm_w1); prefetch_tmap(&tm_wp);
      prefetch_tmap(&tm_a2); prefetch_tmap(&tm_wo); prefetch_tmap(&tm_w2);
#pragma unroll 1
      for (int kb = 0; kb < 10; ++kb) {
        const int slot = kb & 3;
        mbar_wait(bar_empty1 + 8 * slot, ((kb >> 2) & 1) ^ 1);
        const uint32_t fb = bar_full1 + 8 * slot;
        const uint32_t dst = sbase + slot * P1_SLOT;
        mbar_expect_tx(fb, 49152);
        tma_load(dst, &tm_x, fb, kb * 64, row0);
#pragma unroll
        for (int c = 0; c < 4; ++c) tma_load_mc(dst + 16384 + c * 8192 + cm * 4096, &tm_w1, fb, c1 + c * 64, kb * 64 + cm * 32);
      }
      flag_wait(&g_flags[F_WP + j], 16);
      {
        int slot = 2, n3 = 0;
#pragma unroll 1
        for (int i = 0; i < 10; ++i) {
          mbar_wait(bar_empty1 + 8 * slot, ((slot == 2 ? 1 : 2) + n3) & 1);
          const uint32_t fb = bar_full1 + 8 * slot;
          const uint32_t dst = sbase + slot * P1_SLOT;
          mbar_expect_tx(fb, 49152);
          tma_load(dst, &tm_x, fb, i * 64, row0);
#pragma unroll
          for (int c = 0; c < 4; ++c)
            tma_load_mc(dst + 16384 + c * 8192 + cm * 4096, &tm_wp, fb, c * 64, j * DM + i * 64 + cm * 32);
          if (slot == 1) { slot = 2; ++n3; } else { slot = slot == 2 ? 0 : 1; }
        }
      }
      const int kact = kh ? 896 : 0;
      const int na = nkb - 5;
#pragma unroll 1
      for (int t = 0; t < nkb; ++t) {
        const int slot = t & 3;
        if (t < 3) mbar_wait(bar_empty1 + 8 * t, 1);
        else if (t >= 4) mbar_wait(bar_empty2 + 8 * slot, ((t >> 2) & 1) ^ 1);
        const uint32_t fb = bar_full2 + 8 * slot;
        const uint32_t dst = sbase + slot * P2_SLOT;
        mbar_expect_tx(fb, 40960);
        const CUtensorMap* tw = t < na ? &tm_w2 : &tm_wo;
        const int kw = t < na ? kact + t * 64 : kh * 320 + (t - na) * 64;
#pragma unroll
        for (int c = 0; c < 3; ++c) tma_load_mc(dst + 16384 + c * 8192 + cm * 4096, tw, fb, ns * N2 + c * 64, kw + cm * 32);
        if (t == 0) flag_wait(&g_flags[F_ACT + rb], 8);
        if (t == na) flag_wait(&g_flags[F_O + rb], 8);
        tma_load(dst, &tm_a2, fb, t < na ? DM + kw : kw, row0);
      }
    }
  } else {
    const int t = tid - 288;
    {
      const uint4* gp = reinterpret_cast<const uint4*>(gate_w);
      uint4* dst = reinterpret_cast<uint4*>(sgen + GATE_OFF);
      uint4 gv[7];
#pragma unroll
      for (int u = 0; u < 7; ++u) { const int idx = t + 96 * u; gv[u] = __ldg(gp + ((idx < 640 ? idx : 0) >> 3)); }
#pragma unroll
      for (int u = 0; u < 7; ++u) { const int idx = t + 96 * u; if (idx < 640) dst[idx] = gv[u]; }
      if (t < 28) *reinterpret_cast<uint4*>(bias_s + t * 16) = __ldg(reinterpret_cast<const uint4*>(b1 + c1) + t);
      fence_async_smem();
      mbar_arrive(bar_gw);
    }
    if (t == 0) {
      mbar_expect_tx(bar_perm, 19200);
#pragma unroll
      for (int p = 0; p < 3; ++p) tma_load(sbase + PERM_OFF + p * 6400, &tm_wqkv, bar_perm, p * DM + j * 80, rb * 40);
      prefetch_tmap(&tm_wp_st); prefetch_tmap(&tm_act_st); prefetch_tmap(&tm_o_st);
      mbar_wait(bar_perm, 0);
#pragma unroll
      for (int p = 0; p < 3; ++p) tma_store3(&tm_wp_st, sbase + PERM_OFF + p * 6400, 0, p, j * DM + rb * 40);
      bulk_commit();
      bulk_wait_all();
      mbar_arrive(bar_free);
      flag_signal(&g_flags[F_WP + j]);
      mbar_wait(bar_act, 0);
      tma_store(&tm_act_st, sbase + STG_OFF, DM + c1, row0);
      mbar_wait(bar_act + 8, 0);
      tma_store(&tm_act_st, sbase + STG_OFF + 64 * NA * 2, DM + c1, row0 + 64);
      bulk_commit();
      bulk_wait_read();
      mbar_arrive(bar_free);
      bulk_wait_all();
      flag_signal(&g_flags[F_ACT + rb]);
      mbar_wait(bar_dump, 0);
      uint8_t* hp = g_halo + (size_t)(rb * 8 + j) * 5120;
      bulk_store(hp, sbase + STG_OFF + STG_K + 128 * 160, 2560);
      bulk_store(hp + 2560, sbase + STG_OFF + STG_V + 128 * 160, 2560);
      bulk_commit();
      bulk_wait_all();
      flag_signal(&g_flags[F_HALO + rb * 8 + j]);
      if (rb > 0) {
        flag_wait(&g_flags[F_HALO + (rb - 1) * 8 + j], 1);
        mbar_expect_tx(bar_halo, 5120);
        bulk_load(sbase + STG_OFF + STG_K, hp - 8 * 5120, 2560, bar_halo);
        bulk_load(sbase + STG_OFF + STG_V, hp - 8 * 5120 + 2560, 2560, bar_halo);
      } else {
        mbar_arrive(bar_halo);
      }
      mbar_wait(bar_o, 0);
      tma_store(&tm_o_st, sbase + STG_OFF, j * 80, row0);
      bulk_commit();
      bulk_wait_all();
      flag_signal(&g_flags[F_O + rb]);
    }
  }
}

typedef CUresult (*EncodeFn)(CUtensorMap*, CUtensorMapDataType, cuuint32_t, void*, const cuuint64_t*, const cuuint64_t*,
                             const cuuint32_t*, const cuuint32_t*, CUtensorMapInterleave, CUtensorMapSwizzle,
                             CUtensorMapL2promotion, CUtensorMapFloatOOBfill);

void make_map(EncodeFn enc, CUtensorMap* tm, const void* ptr, int rows, int cols, int box_rows, int box_cols, bool swizzle) {
  cuuint64_t gd[2] = {(cuuint64_t)cols, (cuuint64_t)rows};
  cuuint64_t gs[1] = {(cuuint64_t)cols * 2};
  cuuint32_t bx[2] = {(cuuint32_t)box_cols, (cuuint32_t)box_rows};
  cuuint32_t es[2] = {1, 1};
  enc(tm, CU_TENSOR_MAP_DATA_TYPE_BFLOAT16, 2, const_cast<void*>(ptr), gd, gs, bx, es, CU_TENSOR_MAP_INTERLEAVE_NONE,
      swizzle ? CU_TENSOR_MAP_SWIZZLE_128B : CU_TENSOR_MAP_SWIZZLE_NONE, CU_TENSOR_MAP_L2_PROMOTION_L2_128B,
      CU_TENSOR_MAP_FLOAT_OOB_FILL_NONE);
}

}

extern "C" void kernel_launch(void* const* d_in, const int* in_sizes, int n_in, void* d_out, int out_size) {
  const __nv_bfloat16* x = (const __nv_bfloat16*)d_in[0];
  const __nv_bfloat16* wqkv = (const __nv_bfloat16*)d_in[1];
  const __nv_bfloat16* wo = (const __nv_bfloat16*)d_in[2];
  const __nv_bfloat16* w1 = (const __nv_bfloat16*)d_in[4];
  const __nv_bfloat16* b1 = (const __nv_bfloat16*)d_in[5];
  const __nv_bfloat16* w2 = (const __nv_bfloat16*)d_in[6];
  const __nv_bfloat16* gate_w = (const __nv_bfloat16*)d_in[7];

  static EncodeFn enc = nullptr;
  static void* p_a2 = nullptr;
  static void* p_wp = nullptr;
  if (!enc) {
    cudaDriverEntryPointQueryResult qr;
    cudaGetDriverEntryPoint("cuTensorMapEncodeTiled", (void**)&enc, cudaEnableDefault, &qr);
    cudaGetSymbolAddress(&p_a2, g_a2);
    cudaGetSymbolAddress(&p_wp, g_wp);
    cudaFuncSetAttribute(fused_kernel, cudaFuncAttributeMaxDynamicSharedMemorySize, SMEM_BYTES);
  }
  CUtensorMap tm_x, tm_wqkv, tm_w1, tm_a2, tm_wo, tm_w2, tm_act_st, tm_o_st, tm_wp_st, tm_wp;
  make_map(enc, &tm_x, x, SEQ, DM, 128, 64, true);
  make_map(enc, &tm_w1, w1, DM, FF, 32, 64, true);
  make_map(enc, &tm_a2, p_a2, SEQ, KA2, 128, 64, true);
  make_map(enc, &tm_wo, wo, DM, DM, 32, 64, true);
  make_map(enc, &tm_w2, w2, FF, DM, 32, 64, true);
  make_map(enc, &tm_act_st, p_a2, SEQ, KA2, 64, NA, false);
  make_map(enc, &tm_o_st, p_a2, SEQ, KA2, 128, 80, false);
  make_map(enc, &tm_wqkv, wqkv, DM, NQKV, 40, 80, false);
  make_map(enc, &tm_wp, p_wp, 8 * DM, NB, 32, 64, true);
  {
    cuuint64_t gd[3] = {80, 3, (cuuint64_t)(8 * DM)};
    cuuint64_t gs[2] = {160, (cuuint64_t)NB * 2};
    cuuint32_t bx[3] = {80, 1, 40};
    cuuint32_t es[3] = {1, 1, 1};
    enc(&tm_wp_st, CU_TENSOR_MAP_DATA_TYPE_BFLOAT16, 3, p_wp, gd, gs, bx, es, CU_TENSOR_MAP_INTERLEAVE_NONE,
        CU_TENSOR_MAP_SWIZZLE_NONE, CU_TENSOR_MAP_L2_PROMOTION_L2_128B, CU_TENSOR_MAP_FLOAT_OOB_FILL_NONE);
  }
  fused_kernel<<<128, 384, SMEM_BYTES>>>(tm_x, tm_wqkv, tm_w1, tm_a2, tm_wo, tm_w2, tm_act_st, tm_o_st, tm_wp_st, tm_wp,
                                         b1, gate_w,
                                         (__nv_bfloat16*)d_out);
}
```
